```python
import torch

def _softmax(x, axis=-1):
    return torch.softmax(x, dim=axis)
def _gelu(x):
    return torch.nn.functional.gelu(x, approximate="tanh")
def _silu(x):
    return torch.nn.functional.silu(x)
def _sigmoid(x):
    return torch.sigmoid(x)
def _layernorm(x, axis=-1, eps=1e-5):
    m = x.mean(dim=axis, keepdim=True)
    v = x.var(dim=axis, keepdim=True, unbiased=False)
    return (x - m) / torch.sqrt(v + eps)
def _scatter_add(tgt, idx, src, axis=0):
    return tgt.clone().index_add_(axis, idx, src)
def _segment_sum(src, seg, n):
    out = torch.zeros((n,) + src.shape[1:], dtype=src.dtype)
    return out.index_add_(0, seg, src)
def _pad(x, pw):
    flat = tuple(v for pair in reversed(pw) for v in pair)
    return torch.nn.functional.pad(x, flat)

kernel_name = 'concat_heads__sliding_block__linear_attn_block__prompt'

def setup_inputs():

    _w = (lambda a: (lambda t: t.to(torch.bfloat16) if t.is_floating_point() else t)(torch.as_tensor(a)))
    def _A_setup():
        B, S, D = 1, 2048, 576
        return {
            "x": _w((lambda *s: torch.randn(*s, dtype=torch.bfloat16) * 0.2)(B, S, D)),
            "wqkv": _w((lambda *s: torch.randn(*s, dtype=torch.bfloat16) * 0.2)(D, 3 * D)),
            "wo": _w((lambda *s: torch.randn(*s, dtype=torch.bfloat16) * 0.05)(D, D)),
        }
    _A_in = _A_setup()

    def _B_setup():
        B, S, D = 1, 2048, 576
        return {
            "x": _w((lambda *s: torch.randn(*s, dtype=torch.bfloat16) * 0.05)(B, S, D)),
            "wqkv": _w((lambda *s: torch.randn(*s, dtype=torch.bfloat16) * 0.8)(D, 3 * D)),
            "wo": _w((lambda *s: torch.randn(*s, dtype=torch.bfloat16) * 0.8)(D, D)),
        }
    _B_in = _B_setup()

    return {
        "A_x": _A_in["x"],
        "A_wqkv": _A_in["wqkv"],
        "A_wo": _A_in["wo"],
        "B_x": _B_in["x"],
        "B_wqkv": _B_in["wqkv"],
        "B_wo": _B_in["wo"],
    }

def reference(A_x, A_wqkv, A_wo, B_x, B_wqkv, B_wo):
    def _A_ref(x, wqkv, wo):
        B, S, D = x.shape
        H = 32; Dh = D // H; W = 256
        qkv = (lambda x, *d: x.permute(*d))((x @ wqkv).reshape(B, S, 3, H, Dh), 2, 0, 3, 1, 4)
        q, k, v = qkv[0], qkv[1], qkv[2]
        scores = torch.einsum("bhqd,bhkd->bhqk", q, k) * (Dh ** -0.5)
        idx = torch.arange(S)
        mask = (idx[:, None] - idx[None, :] >= 0) & (idx[:, None] - idx[None, :] < W)
        scores = torch.where(mask[None, None], scores, -1e9)
        p = _softmax(scores, axis=-1)
        o = torch.einsum("bhqk,bhkd->bhqd", p, v)
        return (lambda x, *d: x.permute(*d))(o, 0, 2, 1, 3).reshape(B, S, D) @ wo

    def _B_ref(x, wqkv, wo):
        B, S, D = x.shape
        H = 32; Dh = D // H
        qkv = (lambda x, *d: x.permute(*d))((x @ wqkv).reshape(B, S, 3, H, Dh), 2, 0, 3, 1, 4)
        q, k, v = qkv[0], qkv[1], qkv[2]
        phi = lambda t: torch.where(t > 0, t + 1, torch.exp(t)) + 1e-6
        pq, pk = phi(q), phi(k)
        kv = torch.einsum("bhsd,bhse->bhde", pk, v)
        z = torch.einsum("bhsd->bhd", pk)
        num = torch.einsum("bhqd,bhde->bhqe", pq, kv)
        den = torch.einsum("bhqd,bhd->bhq", pq, z)[..., None] + 1e-6
        o = num / den
        return (lambda x, *d: x.permute(*d))(o, 0, 2, 1, 3).reshape(B, S, D) @ wo

    a = _A_ref(A_x, A_wqkv, A_wo)
    b = _B_ref(B_x, B_wqkv, B_wo)
    return torch.concatenate([a, b], axis=-1)
```

```cpp
#include <cuda_runtime.h>
#include <cuda_bf16.h>
#include <cuda.h>
#include <stdint.h>

static constexpr int KVPIECES = 3;
static constexpr int DEPHASE = 350;
static constexpr int OSH = 2;
static constexpr int THROTTLE = 1;
static constexpr int WODELAY = 300;
static constexpr int PUBLATE = 8;
static constexpr int WPREF = 2;
static constexpr int WAITLOG = 20;

namespace {

constexpr int SEQ = 2048, NT = 16, NG = 8;
constexpr int NTHREADS = 384;

constexpr int XS = 4, WS = 7;
__host__ __device__ constexpr uint32_t slot_addr(int i) { return i < 9 ? i * 16384u : 190464u + (i - 9) * 16384u; }
constexpr uint32_t SM_HALO  = 0;
constexpr uint32_t SM_HALOV = 36864;
constexpr uint32_t SM_PQ    = 86016;
constexpr uint32_t SM_PK    = 104448;
constexpr uint32_t SM_VB    = 122880;
constexpr uint32_t SM_KVOUT = 213504 + 6 * 2048;
constexpr uint32_t SM_OSB   = SM_VB;
constexpr uint32_t SM_OWN   = 147456;
constexpr uint32_t SM_OWNV  = SM_OWN + 9 * 2048;
constexpr uint32_t SM_BMAT  = 200704;
constexpr uint32_t SM_OSA   = 213504;
constexpr uint32_t SM_BAR   = 231936;
constexpr uint32_t SM_TOTAL = 232448;
constexpr int OS = 5, OWS = 5;
__host__ __device__ constexpr uint32_t op_o_half(int s, int h) {
    return s == 0 ? (h ? 8192u : 0u) : s == 1 ? (h ? 174080u : 165888u) : s == 2 ? (h ? 61440u : 16384u) : s == 3 ? (h ? 77824u : 69632u) : (h ? 182272u : 24576u);
}
__host__ __device__ constexpr uint32_t op_w_slot(int s) { return s == 0 ? 90112u : s == 1 ? 114688u : s == 2 ? 36864u : s == 3 ? 139264u : 190464u; }

enum { B_XFULL = 0, B_XEMPTY = 4, B_WFULL = 8, B_WEMPTY = 15, B_KVPUB = 22, B_HALO0 = 23, B_HALO1 = 24, B_KVOUT = 25, B_BMAT = 26, B_OB = 27,
       B_OA = 28, B_OPFULL = 32, B_OPEMPTY = 59, B_OSAF = 40, B_HALO2 = 41, B_ATTN = 42, B_KVTOT = 43, B_EARLY = 44, B_EARLY2 = 45, B_WOFULL = 46, B_WOEMPTY = 51,
       B_RDONE = 56, B_WOGO = 57, B_PUBGO = 58, B_COUNT = 63 };
__device__ __forceinline__ uint32_t bar_count(int i) {
    constexpr unsigned long long M8 = (0xFull << B_XEMPTY) | (1ull << B_KVPUB) | (1ull << B_KVOUT) | (1ull << B_OB) | (0xFull << B_OA) | (0x1Full << B_WOEMPTY);
    constexpr unsigned long long M16 = (0x7Full << B_WEMPTY) | (0xFull << B_OPEMPTY) | (1ull << B_ATTN) | (1ull << B_EARLY) | (1ull << B_EARLY2);
    constexpr unsigned long long M33 = (0x7Full << B_WFULL) | (0x1Full << B_WOFULL);
    constexpr unsigned long long M3 = 1ull << B_BMAT;
    return 1u + 2u * (uint32_t)((M3 >> i) & 1) + 7u * (uint32_t)((M8 >> i) & 1) + 15u * (uint32_t)((M16 >> i) & 1) + 32u * (uint32_t)((M33 >> i) & 1);
}

__device__ __align__(1024) uint8_t g_kv[NG * 21 * SEQ * 16];
__device__ __align__(1024) uint8_t g_oa[72 * SEQ * 16];
__device__ __align__(1024) uint8_t g_ob[72 * SEQ * 16];
__device__ __align__(128) float g_kvsum[2 * NG * 1440];
__device__ uint32_t g_flagKV[NT * NG * 8];
__device__ uint32_t g_cntKV[NG * 32];
__device__ __align__(128) uint32_t g_cntOA[NT * 32];
__device__ uint32_t g_cntOB[NT * 32];
__device__ uint32_t g_epoch[NT * NG];
__device__ uint32_t g_qstash[NT * NG * 8 * 4 * 192];

struct alignas(64) Params {
    CUtensorMap tmXA, tmXB, tmWA, tmWB, tmOA, tmOB, tmWoA, tmWoB, tmOut;
    CUtensorMap tmHaloK, tmHaloV, tmKVst, tmOAst2, tmOAst3, tmOBst;
    const __nv_bfloat16 *wA, *wB, *woA, *woB;
};

__device__ __forceinline__ void wg_fence() { asm volatile("wgmma.fence.sync.aligned;" ::: "memory"); }
__device__ __forceinline__ void wg_commit() { asm volatile("wgmma.commit_group.sync.aligned;" ::: "memory"); }
template <int N> __device__ __forceinline__ void wg_wait() { asm volatile("wgmma.wait_group.sync.aligned %0;" ::"n"(N) : "memory"); }
template <int N> __device__ __forceinline__ void pin(float (&d)[N]) {
#pragma unroll
    for (int i = 0; i < N; i++) asm volatile("" : "+f"(d[i])::"memory");
}
template <int N> __device__ __forceinline__ void pin(uint32_t (&d)[N]) {
#pragma unroll
    for (int i = 0; i < N; i++) asm volatile("" : "+r"(d[i])::"memory");
}
__device__ __forceinline__ void mbar_init(uint32_t b, uint32_t c) { asm volatile("mbarrier.init.shared::cta.b64 [%0], %1;" ::"r"(b), "r"(c) : "memory"); }
__device__ __forceinline__ void mbar_expect(uint32_t b, uint32_t bytes) { asm volatile("mbarrier.arrive.expect_tx.shared::cta.b64 _, [%0], %1;" ::"r"(b), "r"(bytes) : "memory"); }
__device__ __forceinline__ void mbar_arrive(uint32_t b) { asm volatile("mbarrier.arrive.shared::cta.b64 _, [%0];" ::"r"(b) : "memory"); }
__device__ __forceinline__ void mbar_arrive_remote(uint32_t b, uint32_t cta) {
    asm volatile("{\n.reg .b32 ra;\nmapa.shared::cluster.u32 ra, %0, %1;\nmbarrier.arrive.shared::cluster.b64 _, [ra];\n}" ::"r"(b), "r"(cta) : "memory");
}
__device__ __forceinline__ void mbar_wait(uint32_t b, uint32_t ph) {
    asm volatile("{\n.reg .pred p;\n.reg .u32 c;\nmov.u32 c, 0;\n"
                 "WAIT_%=:\nmbarrier.try_wait.parity.shared::cta.b64 p, [%0], %1;\n@p bra.uni DONE_%=;\n"
                 "add.u32 c, c, 1;\nsetp.lt.u32 p, c, %2;\n@p bra.uni WAIT_%=;\nDONE_%=:\n}" ::"r"(b), "r"(ph), "n"(1 << WAITLOG) : "memory");
}
__device__ __forceinline__ bool elect_one() {
    uint32_t pred;
    asm volatile("{\n.reg .pred p;\nelect.sync _|p, 0xffffffff;\nselp.u32 %0, 1, 0, p;\n}" : "=r"(pred));
    return pred != 0;
}
__device__ __forceinline__ void fence_async_smem() { asm volatile("fence.proxy.async.shared::cta;" ::: "memory"); }
__device__ __forceinline__ void named_sync(int id, int n) { asm volatile("bar.sync %0, %1;" ::"r"(id), "r"(n) : "memory"); }
__device__ __forceinline__ uint32_t ld_flag(const uint32_t* p) { uint32_t v; asm volatile("ld.relaxed.gpu.global.u32 %0, [%1];" : "=r"(v) : "l"(p) : "memory"); return v; }
__device__ __forceinline__ void poll_ge(const uint32_t* p, uint32_t target) {
#pragma unroll 1
    for (int it = 0; it < (1 << WAITLOG); it++) { if ((int)(ld_flag(p) - target) >= 0) break; __nanosleep(20); }
}
__device__ __forceinline__ void red_add_flag(uint32_t* p, uint32_t v) { asm volatile("red.relaxed.gpu.global.add.u32 [%0], %1;" ::"l"(p), "r"(v) : "memory"); }
__device__ __forceinline__ void st_flag(uint32_t* p, uint32_t v) { asm volatile("st.relaxed.gpu.global.u32 [%0], %1;" ::"l"(p), "r"(v) : "memory"); }
__device__ __forceinline__ void tma2d(uint32_t dst, const CUtensorMap* m, int c0, int c1, uint32_t bar) {
    asm volatile("cp.async.bulk.tensor.2d.shared::cluster.global.mbarrier::complete_tx::bytes [%0], [%1, {%3, %4}], [%2];" ::"r"(dst), "l"(m), "r"(bar), "r"(c0), "r"(c1) : "memory");
}
__device__ __forceinline__ void tma3d(uint32_t dst, const CUtensorMap* m, int c0, int c1, int c2, uint32_t bar) {
    asm volatile("cp.async.bulk.tensor.3d.shared::cluster.global.mbarrier::complete_tx::bytes [%0], [%1, {%3, %4, %5}], [%2];" ::"r"(dst), "l"(m), "r"(bar), "r"(c0), "r"(c1), "r"(c2) : "memory");
}
__device__ __forceinline__ void tma3d_mc(uint32_t dst, const CUtensorMap* m, int c0, int c1, int c2, uint32_t bar) {
    asm volatile("cp.async.bulk.tensor.3d.shared::cluster.global.mbarrier::complete_tx::bytes.multicast::cluster [%0], [%1, {%3, %4, %5}], [%2], %6;" ::"r"(dst), "l"(m), "r"(bar), "r"(c0), "r"(c1), "r"(c2), "h"((uint16_t)3) : "memory");
}
__device__ __forceinline__ void tma4d(uint32_t dst, const CUtensorMap* m, int c0, int c1, int c2, int c3, uint32_t bar) {
    asm volatile("cp.async.bulk.tensor.4d.shared::cluster.global.mbarrier::complete_tx::bytes [%0], [%1, {%3, %4, %5, %6}], [%2];" ::"r"(dst), "l"(m), "r"(bar), "r"(c0), "r"(c1), "r"(c2), "r"(c3) : "memory");
}
__device__ __forceinline__ void tma4d_mc(uint32_t dst, const CUtensorMap* m, int c0, int c1, int c2, int c3, uint32_t bar) {
    asm volatile("cp.async.bulk.tensor.4d.shared::cluster.global.mbarrier::complete_tx::bytes.multicast::cluster [%0], [%1, {%3, %4, %5, %6}], [%2], %7;" ::"r"(dst), "l"(m), "r"(bar), "r"(c0), "r"(c1), "r"(c2), "r"(c3), "h"((uint16_t)3) : "memory");
}
__device__ __forceinline__ void tma4d_store(const CUtensorMap* m, int c0, int c1, int c2, int c3, uint32_t src) {
    asm volatile("cp.async.bulk.tensor.4d.global.shared::cta.bulk_group [%0, {%2, %3, %4, %5}], [%1];" ::"l"(m), "r"(src), "r"(c0), "r"(c1), "r"(c2), "r"(c3) : "memory");
}
__device__ __forceinline__ void tma3d_store(const CUtensorMap* m, int c0, int c1, int c2, uint32_t src) {
    asm volatile("cp.async.bulk.tensor.3d.global.shared::cta.bulk_group [%0, {%2, %3, %4}], [%1];" ::"l"(m), "r"(src), "r"(c0), "r"(c1), "r"(c2) : "memory");
}
__device__ __forceinline__ void tma2d_store(const CUtensorMap* m, int c0, int c1, uint32_t src) {
    asm volatile("cp.async.bulk.tensor.2d.global.shared::cta.bulk_group [%0, {%2, %3}], [%1];" ::"l"(m), "r"(src), "r"(c0), "r"(c1) : "memory");
}
__device__ __forceinline__ void bulk_load(uint32_t dst, const void* src, uint32_t bytes, uint32_t bar) {
    asm volatile("cp.async.bulk.shared::cluster.global.mbarrier::complete_tx::bytes [%0], [%1], %2, [%3];" ::"r"(dst), "l"(src), "r"(bytes), "r"(bar) : "memory");
}
__device__ __forceinline__ void bulk_reduce_f32(void* dst, uint32_t src, uint32_t bytes) {
    asm volatile("cp.reduce.async.bulk.global.shared::cta.bulk_group.add.f32 [%0], [%1], %2;" ::"l"(dst), "r"(src), "r"(bytes) : "memory");
}
__device__ __forceinline__ void cp_async16(uint32_t dst, const void* src) { asm volatile("cp.async.cg.shared.global [%0], [%1], 16;" ::"r"(dst), "l"(src) : "memory"); }
__device__ __forceinline__ void bulk_commit() { asm volatile("cp.async.bulk.commit_group;" ::: "memory"); }
__device__ __forceinline__ void bulk_wait0() { asm volatile("cp.async.bulk.wait_group 0;" ::: "memory"); }
__device__ __forceinline__ void stsm4(uint32_t a, uint32_t r0, uint32_t r1, uint32_t r2, uint32_t r3) {
    asm volatile("stmatrix.sync.aligned.m8n8.x4.shared.b16 [%0], {%1,%2,%3,%4};" ::"r"(a), "r"(r0), "r"(r1), "r"(r2), "r"(r3) : "memory");
}
__device__ __forceinline__ void stsm2(uint32_t a, uint32_t r0, uint32_t r1) {
    asm volatile("stmatrix.sync.aligned.m8n8.x2.shared.b16 [%0], {%1,%2};" ::"r"(a), "r"(r0), "r"(r1) : "memory");
}
__device__ __forceinline__ void sts32(uint32_t a, uint32_t v) { asm volatile("st.shared.u32 [%0], %1;" ::"r"(a), "r"(v) : "memory"); }
__device__ __forceinline__ void sts32p(uint32_t a, uint32_t v, bool p) {
    asm volatile("{\n.reg .pred p;\nsetp.ne.b32 p, %2, 0;\n@p st.shared.u32 [%0], %1;\n}" ::"r"(a), "r"(v), "r"((int)p) : "memory");
}
__device__ __forceinline__ void sts64p(uint32_t a, float x, float y, bool p) {
    asm volatile("{\n.reg .pred p;\nsetp.ne.b32 p, %3, 0;\n@p st.shared.v2.f32 [%0], {%1,%2};\n}" ::"r"(a), "f"(x), "f"(y), "r"((int)p) : "memory");
}
__device__ __forceinline__ void sts128(uint32_t a, uint4 v) { asm volatile("st.shared.v4.u32 [%0], {%1,%2,%3,%4};" ::"r"(a), "r"(v.x), "r"(v.y), "r"(v.z), "r"(v.w) : "memory"); }
__device__ __forceinline__ uint4 lds128(uint32_t a) { uint4 v; asm volatile("ld.shared.v4.u32 {%0,%1,%2,%3}, [%4];" : "=r"(v.x), "=r"(v.y), "=r"(v.z), "=r"(v.w) : "r"(a) : "memory"); return v; }
__device__ __forceinline__ uint32_t opaque_zero() { uint32_t z; asm volatile("mov.u32 %0, 0;" : "=r"(z)); return z; }
__device__ __forceinline__ float ex2(float x) { float y; asm("ex2.approx.ftz.f32 %0, %1;" : "=f"(y) : "f"(x)); return y; }
__device__ __forceinline__ float rcp(float x) { float y; asm("rcp.approx.ftz.f32 %0, %1;" : "=f"(y) : "f"(x)); return y; }
__device__ __forceinline__ uint32_t pack(float lo, float hi) { uint32_t r; asm("cvt.rn.bf16x2.f32 %0, %1, %2;" : "=r"(r) : "f"(hi), "f"(lo)); return r; }
__device__ __forceinline__ float bf_lo(uint32_t v) { return __uint_as_float(v << 16); }
__device__ __forceinline__ float bf_hi(uint32_t v) { return __uint_as_float(v & 0xffff0000u); }

__device__ __forceinline__ void mma_gemm1(float (&d)[108], uint32_t alo, uint32_t ahi, uint32_t blo, uint32_t bhi, uint32_t sc) {
  asm volatile("{\n.reg .pred p;\n.reg .b64 da, db;\nsetp.ne.b32 p, %112, 0;\nmov.b64 da, {%108, %109};\nmov.b64 db, {%110, %111};\n"
    "wgmma.mma_async.sync.aligned.m64n216k16.f32.bf16.bf16 {%0, %1, %2, %3, %4, %5, %6, %7, %8, %9, %10, %11, %12, %13, %14, %15, %16, %17, %18, %19, %20, %21, %22, %23, %24, %25, %26, %27, %28, %29, %30, %31, %32, %33, %34, %35, %36, %37, %38, %39, %40, %41, %42, %43, %44, %45, %46, %47, %48, %49, %50, %51, %52, %53, %54, %55, %56, %57, %58, %59, %60, %61, %62, %63, %64, %65, %66, %67, %68, %69, %70, %71, %72, %73, %74, %75, %76, %77, %78, %79, %80, %81, %82, %83, %84, %85, %86, %87, %88, %89, %90, %91, %92, %93, %94, %95, %96, %97, %98, %99, %100, %101, %102, %103, %104, %105, %106, %107}, da, db, p, 1, 1, 0, 1;\n}\n"
    : "+f"(d[0]), "+f"(d[1]), "+f"(d[2]), "+f"(d[3]), "+f"(d[4]), "+f"(d[5]), "+f"(d[6]), "+f"(d[7]),
      "+f"(d[8]), "+f"(d[9]), "+f"(d[10]), "+f"(d[11]), "+f"(d[12]), "+f"(d[13]), "+f"(d[14]), "+f"(d[15]),
      "+f"(d[16]), "+f"(d[17]), "+f"(d[18]), "+f"(d[19]), "+f"(d[20]), "+f"(d[21]), "+f"(d[22]), "+f"(d[23]),
      "+f"(d[24]), "+f"(d[25]), "+f"(d[26]), "+f"(d[27]), "+f"(d[28]), "+f"(d[29]), "+f"(d[30]), "+f"(d[31]),
      "+f"(d[32]), "+f"(d[33]), "+f"(d[34]), "+f"(d[35]), "+f"(d[36]), "+f"(d[37]), "+f"(d[38]), "+f"(d[39]),
      "+f"(d[40]), "+f"(d[41]), "+f"(d[42]), "+f"(d[43]), "+f"(d[44]), "+f"(d[45]), "+f"(d[46]), "+f"(d[47]),
      "+f"(d[48]), "+f"(d[49]), "+f"(d[50]), "+f"(d[51]), "+f"(d[52]), "+f"(d[53]), "+f"(d[54]), "+f"(d[55]),
      "+f"(d[56]), "+f"(d[57]), "+f"(d[58]), "+f"(d[59]), "+f"(d[60]), "+f"(d[61]), "+f"(d[62]), "+f"(d[63]),
      "+f"(d[64]), "+f"(d[65]), "+f"(d[66]), "+f"(d[67]), "+f"(d[68]), "+f"(d[69]), "+f"(d[70]), "+f"(d[71]),
      "+f"(d[72]), "+f"(d[73]), "+f"(d[74]), "+f"(d[75]), "+f"(d[76]), "+f"(d[77]), "+f"(d[78]), "+f"(d[79]),
      "+f"(d[80]), "+f"(d[81]), "+f"(d[82]), "+f"(d[83]), "+f"(d[84]), "+f"(d[85]), "+f"(d[86]), "+f"(d[87]),
      "+f"(d[88]), "+f"(d[89]), "+f"(d[90]), "+f"(d[91]), "+f"(d[92]), "+f"(d[93]), "+f"(d[94]), "+f"(d[95]),
      "+f"(d[96]), "+f"(d[97]), "+f"(d[98]), "+f"(d[99]), "+f"(d[100]), "+f"(d[101]), "+f"(d[102]), "+f"(d[103]),
      "+f"(d[104]), "+f"(d[105]), "+f"(d[106]), "+f"(d[107])
    : "r"(alo), "r"(ahi), "r"(blo), "r"(bhi), "r"(sc));
}
__device__ __forceinline__ void mma_kv_z(float (&d)[40], uint32_t alo, uint32_t ahi, uint32_t blo, uint32_t bhi) {
  asm volatile("{\n.reg .pred p;\n.reg .b64 da, db;\nsetp.ne.b32 p, 0, 0;\nmov.b64 da, {%40, %41};\nmov.b64 db, {%42, %43};\n"
    "wgmma.mma_async.sync.aligned.m64n80k16.f32.bf16.bf16 {%0, %1, %2, %3, %4, %5, %6, %7, %8, %9, %10, %11, %12, %13, %14, %15, %16, %17, %18, %19, %20, %21, %22, %23, %24, %25, %26, %27, %28, %29, %30, %31, %32, %33, %34, %35, %36, %37, %38, %39}, da, db, p, 1, 1, 1, 1;\n}\n"
    : "+f"(d[0]), "+f"(d[1]), "+f"(d[2]), "+f"(d[3]), "+f"(d[4]), "+f"(d[5]), "+f"(d[6]), "+f"(d[7]),
      "+f"(d[8]), "+f"(d[9]), "+f"(d[10]), "+f"(d[11]), "+f"(d[12]), "+f"(d[13]), "+f"(d[14]), "+f"(d[15]),
      "+f"(d[16]), "+f"(d[17]), "+f"(d[18]), "+f"(d[19]), "+f"(d[20]), "+f"(d[21]), "+f"(d[22]), "+f"(d[23]),
      "+f"(d[24]), "+f"(d[25]), "+f"(d[26]), "+f"(d[27]), "+f"(d[28]), "+f"(d[29]), "+f"(d[30]), "+f"(d[31]),
      "+f"(d[32]), "+f"(d[33]), "+f"(d[34]), "+f"(d[35]), "+f"(d[36]), "+f"(d[37]), "+f"(d[38]), "+f"(d[39])
    : "r"(alo), "r"(ahi), "r"(blo), "r"(bhi));
}
__device__ __forceinline__ void mma_kv(float (&d)[40], uint32_t alo, uint32_t ahi, uint32_t blo, uint32_t bhi) {
  asm volatile("{\n.reg .pred p;\n.reg .b64 da, db;\nsetp.ne.b32 p, 1, 0;\nmov.b64 da, {%40, %41};\nmov.b64 db, {%42, %43};\n"
    "wgmma.mma_async.sync.aligned.m64n80k16.f32.bf16.bf16 {%0, %1, %2, %3, %4, %5, %6, %7, %8, %9, %10, %11, %12, %13, %14, %15, %16, %17, %18, %19, %20, %21, %22, %23, %24, %25, %26, %27, %28, %29, %30, %31, %32, %33, %34, %35, %36, %37, %38, %39}, da, db, p, 1, 1, 1, 1;\n}\n"
    : "+f"(d[0]), "+f"(d[1]), "+f"(d[2]), "+f"(d[3]), "+f"(d[4]), "+f"(d[5]), "+f"(d[6]), "+f"(d[7]),
      "+f"(d[8]), "+f"(d[9]), "+f"(d[10]), "+f"(d[11]), "+f"(d[12]), "+f"(d[13]), "+f"(d[14]), "+f"(d[15]),
      "+f"(d[16]), "+f"(d[17]), "+f"(d[18]), "+f"(d[19]), "+f"(d[20]), "+f"(d[21]), "+f"(d[22]), "+f"(d[23]),
      "+f"(d[24]), "+f"(d[25]), "+f"(d[26]), "+f"(d[27]), "+f"(d[28]), "+f"(d[29]), "+f"(d[30]), "+f"(d[31]),
      "+f"(d[32]), "+f"(d[33]), "+f"(d[34]), "+f"(d[35]), "+f"(d[36]), "+f"(d[37]), "+f"(d[38]), "+f"(d[39])
    : "r"(alo), "r"(ahi), "r"(blo), "r"(bhi));
}
__device__ __forceinline__ void mma_os_z(float (&d)[40], uint32_t alo, uint32_t ahi, uint32_t blo, uint32_t bhi) {
  asm volatile("{\n.reg .pred p;\n.reg .b64 da, db;\nsetp.ne.b32 p, 0, 0;\nmov.b64 da, {%40, %41};\nmov.b64 db, {%42, %43};\n"
    "wgmma.mma_async.sync.aligned.m64n80k16.f32.bf16.bf16 {%0, %1, %2, %3, %4, %5, %6, %7, %8, %9, %10, %11, %12, %13, %14, %15, %16, %17, %18, %19, %20, %21, %22, %23, %24, %25, %26, %27, %28, %29, %30, %31, %32, %33, %34, %35, %36, %37, %38, %39}, da, db, p, 1, 1, 0, 0;\n}\n"
    : "+f"(d[0]), "+f"(d[1]), "+f"(d[2]), "+f"(d[3]), "+f"(d[4]), "+f"(d[5]), "+f"(d[6]), "+f"(d[7]),
      "+f"(d[8]), "+f"(d[9]), "+f"(d[10]), "+f"(d[11]), "+f"(d[12]), "+f"(d[13]), "+f"(d[14]), "+f"(d[15]),
      "+f"(d[16]), "+f"(d[17]), "+f"(d[18]), "+f"(d[19]), "+f"(d[20]), "+f"(d[21]), "+f"(d[22]), "+f"(d[23]),
      "+f"(d[24]), "+f"(d[25]), "+f"(d[26]), "+f"(d[27]), "+f"(d[28]), "+f"(d[29]), "+f"(d[30]), "+f"(d[31]),
      "+f"(d[32]), "+f"(d[33]), "+f"(d[34]), "+f"(d[35]), "+f"(d[36]), "+f"(d[37]), "+f"(d[38]), "+f"(d[39])
    : "r"(alo), "r"(ahi), "r"(blo), "r"(bhi));
}
__device__ __forceinline__ void mma_os(float (&d)[40], uint32_t alo, uint32_t ahi, uint32_t blo, uint32_t bhi) {
  asm volatile("{\n.reg .pred p;\n.reg .b64 da, db;\nsetp.ne.b32 p, 1, 0;\nmov.b64 da, {%40, %41};\nmov.b64 db, {%42, %43};\n"
    "wgmma.mma_async.sync.aligned.m64n80k16.f32.bf16.bf16 {%0, %1, %2, %3, %4, %5, %6, %7, %8, %9, %10, %11, %12, %13, %14, %15, %16, %17, %18, %19, %20, %21, %22, %23, %24, %25, %26, %27, %28, %29, %30, %31, %32, %33, %34, %35, %36, %37, %38, %39}, da, db, p, 1, 1, 0, 0;\n}\n"
    : "+f"(d[0]), "+f"(d[1]), "+f"(d[2]), "+f"(d[3]), "+f"(d[4]), "+f"(d[5]), "+f"(d[6]), "+f"(d[7]),
      "+f"(d[8]), "+f"(d[9]), "+f"(d[10]), "+f"(d[11]), "+f"(d[12]), "+f"(d[13]), "+f"(d[14]), "+f"(d[15]),
      "+f"(d[16]), "+f"(d[17]), "+f"(d[18]), "+f"(d[19]), "+f"(d[20]), "+f"(d[21]), "+f"(d[22]), "+f"(d[23]),
      "+f"(d[24]), "+f"(d[25]), "+f"(d[26]), "+f"(d[27]), "+f"(d[28]), "+f"(d[29]), "+f"(d[30]), "+f"(d[31]),
      "+f"(d[32]), "+f"(d[33]), "+f"(d[34]), "+f"(d[35]), "+f"(d[36]), "+f"(d[37]), "+f"(d[38]), "+f"(d[39])
    : "r"(alo), "r"(ahi), "r"(blo), "r"(bhi));
}
__device__ __forceinline__ void mma_qk_z(float (&d)[32], uint32_t a0, uint32_t a1, uint32_t a2, uint32_t a3, uint32_t blo, uint32_t bhi) {
  asm volatile("{\n.reg .pred p;\n.reg .b64 db;\nsetp.ne.b32 p, 0, 0;\nmov.b64 db, {%36, %37};\n"
    "wgmma.mma_async.sync.aligned.m64n64k16.f32.bf16.bf16 {%0, %1, %2, %3, %4, %5, %6, %7, %8, %9, %10, %11, %12, %13, %14, %15, %16, %17, %18, %19, %20, %21, %22, %23, %24, %25, %26, %27, %28, %29, %30, %31}, {%32,%33,%34,%35}, db, p, 1, 1, 0;\n}\n"
    : "+f"(d[0]), "+f"(d[1]), "+f"(d[2]), "+f"(d[3]), "+f"(d[4]), "+f"(d[5]), "+f"(d[6]), "+f"(d[7]),
      "+f"(d[8]), "+f"(d[9]), "+f"(d[10]), "+f"(d[11]), "+f"(d[12]), "+f"(d[13]), "+f"(d[14]), "+f"(d[15]),
      "+f"(d[16]), "+f"(d[17]), "+f"(d[18]), "+f"(d[19]), "+f"(d[20]), "+f"(d[21]), "+f"(d[22]), "+f"(d[23]),
      "+f"(d[24]), "+f"(d[25]), "+f"(d[26]), "+f"(d[27]), "+f"(d[28]), "+f"(d[29]), "+f"(d[30]), "+f"(d[31])
    : "r"(a0), "r"(a1), "r"(a2), "r"(a3), "r"(blo), "r"(bhi));
}
__device__ __forceinline__ void mma_qk(float (&d)[32], uint32_t a0, uint32_t a1, uint32_t a2, uint32_t a3, uint32_t blo, uint32_t bhi) {
  asm volatile("{\n.reg .pred p;\n.reg .b64 db;\nsetp.ne.b32 p, 1, 0;\nmov.b64 db, {%36, %37};\n"
    "wgmma.mma_async.sync.aligned.m64n64k16.f32.bf16.bf16 {%0, %1, %2, %3, %4, %5, %6, %7, %8, %9, %10, %11, %12, %13, %14, %15, %16, %17, %18, %19, %20, %21, %22, %23, %24, %25, %26, %27, %28, %29, %30, %31}, {%32,%33,%34,%35}, db, p, 1, 1, 0;\n}\n"
    : "+f"(d[0]), "+f"(d[1]), "+f"(d[2]), "+f"(d[3]), "+f"(d[4]), "+f"(d[5]), "+f"(d[6]), "+f"(d[7]),
      "+f"(d[8]), "+f"(d[9]), "+f"(d[10]), "+f"(d[11]), "+f"(d[12]), "+f"(d[13]), "+f"(d[14]), "+f"(d[15]),
      "+f"(d[16]), "+f"(d[17]), "+f"(d[18]), "+f"(d[19]), "+f"(d[20]), "+f"(d[21]), "+f"(d[22]), "+f"(d[23]),
      "+f"(d[24]), "+f"(d[25]), "+f"(d[26]), "+f"(d[27]), "+f"(d[28]), "+f"(d[29]), "+f"(d[30]), "+f"(d[31])
    : "r"(a0), "r"(a1), "r"(a2), "r"(a3), "r"(blo), "r"(bhi));
}
__device__ __forceinline__ void mma_pv_z(float (&d)[12], uint32_t a0, uint32_t a1, uint32_t a2, uint32_t a3, uint32_t blo, uint32_t bhi) {
  asm volatile("{\n.reg .pred p;\n.reg .b64 db;\nsetp.ne.b32 p, 0, 0;\nmov.b64 db, {%16, %17};\n"
    "wgmma.mma_async.sync.aligned.m64n24k16.f32.bf16.bf16 {%0, %1, %2, %3, %4, %5, %6, %7, %8, %9, %10, %11}, {%12,%13,%14,%15}, db, p, 1, 1, 1;\n}\n"
    : "+f"(d[0]), "+f"(d[1]), "+f"(d[2]), "+f"(d[3]), "+f"(d[4]), "+f"(d[5]), "+f"(d[6]), "+f"(d[7]),
      "+f"(d[8]), "+f"(d[9]), "+f"(d[10]), "+f"(d[11])
    : "r"(a0), "r"(a1), "r"(a2), "r"(a3), "r"(blo), "r"(bhi));
}
__device__ __forceinline__ void mma_pv(float (&d)[12], uint32_t a0, uint32_t a1, uint32_t a2, uint32_t a3, uint32_t blo, uint32_t bhi) {
  asm volatile("{\n.reg .pred p;\n.reg .b64 db;\nsetp.ne.b32 p, 1, 0;\nmov.b64 db, {%16, %17};\n"
    "wgmma.mma_async.sync.aligned.m64n24k16.f32.bf16.bf16 {%0, %1, %2, %3, %4, %5, %6, %7, %8, %9, %10, %11}, {%12,%13,%14,%15}, db, p, 1, 1, 1;\n}\n"
    : "+f"(d[0]), "+f"(d[1]), "+f"(d[2]), "+f"(d[3]), "+f"(d[4]), "+f"(d[5]), "+f"(d[6]), "+f"(d[7]),
      "+f"(d[8]), "+f"(d[9]), "+f"(d[10]), "+f"(d[11])
    : "r"(a0), "r"(a1), "r"(a2), "r"(a3), "r"(blo), "r"(bhi));
}
__device__ __forceinline__ void mma_op(float (&d)[72], uint32_t alo, uint32_t ahi, uint32_t blo, uint32_t bhi, uint32_t sc) {
  asm volatile("{\n.reg .pred p;\n.reg .b64 da, db;\nsetp.ne.b32 p, %76, 0;\nmov.b64 da, {%72, %73};\nmov.b64 db, {%74, %75};\n"
    "wgmma.mma_async.sync.aligned.m64n144k16.f32.bf16.bf16 {%0, %1, %2, %3, %4, %5, %6, %7, %8, %9, %10, %11, %12, %13, %14, %15, %16, %17, %18, %19, %20, %21, %22, %23, %24, %25, %26, %27, %28, %29, %30, %31, %32, %33, %34, %35, %36, %37, %38, %39, %40, %41, %42, %43, %44, %45, %46, %47, %48, %49, %50, %51, %52, %53, %54, %55, %56, %57, %58, %59, %60, %61, %62, %63, %64, %65, %66, %67, %68, %69, %70, %71}, da, db, p, 1, 1, 0, 1;\n}\n"
    : "+f"(d[0]), "+f"(d[1]), "+f"(d[2]), "+f"(d[3]), "+f"(d[4]), "+f"(d[5]), "+f"(d[6]), "+f"(d[7]),
      "+f"(d[8]), "+f"(d[9]), "+f"(d[10]), "+f"(d[11]), "+f"(d[12]), "+f"(d[13]), "+f"(d[14]), "+f"(d[15]),
      "+f"(d[16]), "+f"(d[17]), "+f"(d[18]), "+f"(d[19]), "+f"(d[20]), "+f"(d[21]), "+f"(d[22]), "+f"(d[23]),
      "+f"(d[24]), "+f"(d[25]), "+f"(d[26]), "+f"(d[27]), "+f"(d[28]), "+f"(d[29]), "+f"(d[30]), "+f"(d[31]),
      "+f"(d[32]), "+f"(d[33]), "+f"(d[34]), "+f"(d[35]), "+f"(d[36]), "+f"(d[37]), "+f"(d[38]), "+f"(d[39]),
      "+f"(d[40]), "+f"(d[41]), "+f"(d[42]), "+f"(d[43]), "+f"(d[44]), "+f"(d[45]), "+f"(d[46]), "+f"(d[47]),
      "+f"(d[48]), "+f"(d[49]), "+f"(d[50]), "+f"(d[51]), "+f"(d[52]), "+f"(d[53]), "+f"(d[54]), "+f"(d[55]),
      "+f"(d[56]), "+f"(d[57]), "+f"(d[58]), "+f"(d[59]), "+f"(d[60]), "+f"(d[61]), "+f"(d[62]), "+f"(d[63]),
      "+f"(d[64]), "+f"(d[65]), "+f"(d[66]), "+f"(d[67]), "+f"(d[68]), "+f"(d[69]), "+f"(d[70]), "+f"(d[71])
    : "r"(alo), "r"(ahi), "r"(blo), "r"(bhi), "r"(sc));
}


__device__ __forceinline__ uint32_t da(uint32_t addr) { return (addr & 0x3FFFFu) >> 4; }
constexpr uint32_t HI_SW128 = (1024u >> 4) | (1u << 30);
constexpr float QSCALE = 0.23570226039551584f * 1.4426950408889634f;
constexpr float LOG2E = 1.4426950408889634f;

__device__ __forceinline__ uint32_t slot_addr_rt(int i) { return i < 9 ? i * 16384u : 190464u + (i - 9) * 16384u; }

__device__ __forceinline__ void gemm1_mainloop(float (&acc)[108], uint32_t sb, uint32_t bars, int it0, int wg, bool elect, uint32_t peer) {
    int xs = it0 % XS, ws = (2 * it0) % WS;
    uint32_t xph = (it0 / XS) & 1, wph = ((2 * it0) / WS) & 1;
    int pws = 0, pxs = 0;
#pragma unroll 1
    for (int s = 0; s < 9; s++) {
        mbar_wait(bars + 8 * (B_XFULL + xs), xph);
        const uint32_t alo = da(sb + xs * 16384 + wg * 8192) | (1u << 16);
#pragma unroll
        for (int h = 0; h < 2; h++) {
            mbar_wait(bars + 8 * (B_WFULL + ws), wph);
            fence_async_smem();
            const uint32_t blo = da(sb + slot_addr_rt(XS + ws)) | ((4096u >> 4) << 16);
            wg_fence();
            mma_gemm1(acc, alo + 4 * h, HI_SW128, blo, HI_SW128, (s | h) != 0);
            mma_gemm1(acc, alo + 4 * h + 2, HI_SW128, blo + 128, HI_SW128, 1);
            wg_commit();
            if (s > 0 || h > 0) {
                wg_wait<1>();
                if (elect) {
                    const uint32_t eb = bars + 8 * (B_WEMPTY + pws);
                    mbar_arrive(eb); mbar_arrive_remote(eb, peer);
                    if (h == 0) mbar_arrive(bars + 8 * (B_XEMPTY + pxs));
                }
            }
            pws = ws;
            if (++ws == WS) { ws = 0; wph ^= 1; }
        }
        pxs = xs;
        if (++xs == XS) { xs = 0; xph ^= 1; }
    }
    wg_wait<0>();
    if (elect) {
        const uint32_t eb = bars + 8 * (B_WEMPTY + pws);
        mbar_arrive(eb); mbar_arrive_remote(eb, peer);
        mbar_arrive(bars + 8 * (B_XEMPTY + pxs));
    }
    pin(acc);
}

__device__ __forceinline__ void rotate_planes(uint32_t (&v)[18], bool odd) {
    const uint32_t l0 = v[16], l1 = v[17];
#pragma unroll
    for (int j = 8; j >= 1; j--) { v[2 * j] = odd ? v[2 * j - 2] : v[2 * j]; v[2 * j + 1] = odd ? v[2 * j - 1] : v[2 * j + 1]; }
    v[0] = odd ? l0 : v[0];
    v[1] = odd ? l1 : v[1];
}

__device__ __forceinline__ void store_tiles(const uint32_t (&v)[18], uint32_t base, uint32_t rowoff, int lane, int odd) {
    const uint32_t la = base + (odd + (lane >> 4)) * 2048 + rowoff;
#pragma unroll
    for (int j = 0; j < 8; j += 2) stsm4(la + j * 2048, v[2 * j], v[2 * j + 1], v[2 * j + 2], v[2 * j + 3]);
    stsm2(base + (odd ? 0 : 8 * 2048) + rowoff, v[16], v[17]);
}
__device__ __forceinline__ void store_planes(const uint32_t (&v)[18], uint32_t lane_addr, uint32_t pstride) {
#pragma unroll
    for (int j = 0; j < 8; j += 2) stsm4(lane_addr + j * pstride, v[2 * j], v[2 * j + 1], v[2 * j + 2], v[2 * j + 3]);
}

__device__ __forceinline__ float phi(float t) { return fmaxf(t, 1e-6f) + ex2(fminf(t * LOG2E, 0.f)); }

__device__ __forceinline__ void attn_slow(uint32_t (&fin)[6], const uint32_t (&q)[6], int hp, int row_local  , int t,
                                          uint32_t sb, int lane) {
    const int c4 = lane & 3;
#pragma unroll 1
    for (int hi = 0; hi < 2; hi++) {
        float qv[24];
#pragma unroll
        for (int jj = 0; jj < 3; jj++) {
            uint32_t mine = hi ? q[2 * jj + 1] : q[2 * jj];
#pragma unroll
            for (int cc = 0; cc < 4; cc++) {
                uint32_t pr = __shfl_sync(0xffffffffu, mine, (lane & ~3) | cc);
                qv[8 * jj + 2 * cc] = bf_lo(pr);
                qv[8 * jj + 2 * cc + 1] = bf_hi(pr);
            }
        }
        const int i = 128 * t + row_local + 8 * hi;
        const int jlo = i - 255 < 0 ? 0 : i - 255;
        const int ubase = 128 * t - 256;
        float m = -INFINITY, l = 0.f, o[18];
#pragma unroll
        for (int n = 0; n < 18; n++) o[n] = 0.f;
#pragma unroll 1
        for (int pass = 0; pass < 2; pass++) {
#pragma unroll 1
            for (int j = jlo + c4; j <= i; j += 4) {
                const int u = j - ubase;
                const uint32_t ps = u < 256 ? 4096u : 2048u;
                const uint32_t ka = (u < 256 ? sb + SM_HALO + u * 16 : sb + SM_OWN + (u - 256) * 16) + 2 * hp * ps;
                float s = 0.f;
#pragma unroll
                for (int jj = 0; jj < 3; jj++) {
                    uint4 kk = lds128(ka + jj * ps);
                    s += qv[8 * jj] * bf_lo(kk.x) + qv[8 * jj + 1] * bf_hi(kk.x) + qv[8 * jj + 2] * bf_lo(kk.y) + qv[8 * jj + 3] * bf_hi(kk.y) +
                         qv[8 * jj + 4] * bf_lo(kk.z) + qv[8 * jj + 5] * bf_hi(kk.z) + qv[8 * jj + 6] * bf_lo(kk.w) + qv[8 * jj + 7] * bf_hi(kk.w);
                }
                if (pass == 0) { m = fmaxf(m, s); continue; }
                const float p = ex2(s - m);
                l += p;
                const uint32_t va = (u < 256 ? sb + SM_HALOV + u * 16 : sb + SM_OWNV + (u - 256) * 16) + 3 * hp * ps;
#pragma unroll
                for (int jj = 0; jj < 2; jj++) {
                    uint4 vv = lds128(va + jj * ps);
                    o[8 * jj] += p * bf_lo(vv.x); o[8 * jj + 1] += p * bf_hi(vv.x); o[8 * jj + 2] += p * bf_lo(vv.y); o[8 * jj + 3] += p * bf_hi(vv.y);
                    o[8 * jj + 4] += p * bf_lo(vv.z); o[8 * jj + 5] += p * bf_hi(vv.z); o[8 * jj + 6] += p * bf_lo(vv.w); o[8 * jj + 7] += p * bf_hi(vv.w);
                }
                const uint4 v3 = lds128(va + 2 * ps);
                o[16] += p * bf_lo(v3.x); o[17] += p * bf_hi(v3.x);
            }
            if (pass == 0) {
                m = fmaxf(m, __shfl_xor_sync(0xffffffffu, m, 1));
                m = fmaxf(m, __shfl_xor_sync(0xffffffffu, m, 2));
            }
        }
        l += __shfl_xor_sync(0xffffffffu, l, 1);
        l += __shfl_xor_sync(0xffffffffu, l, 2);
        const float r = 1.0f / l;
#pragma unroll
        for (int n = 0; n < 18; n++) {
            o[n] += __shfl_xor_sync(0xffffffffu, o[n], 1);
            o[n] += __shfl_xor_sync(0xffffffffu, o[n], 2);
        }
#pragma unroll
        for (int jj = 0; jj < 2; jj++) {
            const float a = c4 == 0 ? o[8 * jj] : c4 == 1 ? o[8 * jj + 2] : c4 == 2 ? o[8 * jj + 4] : o[8 * jj + 6];
            const float b = c4 == 0 ? o[8 * jj + 1] : c4 == 1 ? o[8 * jj + 3] : c4 == 2 ? o[8 * jj + 5] : o[8 * jj + 7];
            const uint32_t pk = pack(a * r, b * r);
            if (hi) fin[2 * jj + 1] = pk; else fin[2 * jj] = pk;
        }
        const uint32_t pk = pack(o[16] * r, o[17] * r);
        if (hi) fin[5] = pk; else fin[4] = pk;
    }
}

__device__ __forceinline__ void attn_store(const uint32_t (&fin)[6], int hp, uint32_t obase  , uint32_t bars, int lane) {
    const int c4 = lane & 3;
    const int col = 18 * hp + 2 * c4;
    const uint32_t a0 = obase + (col >> 3) * 2048 + (col & 7) * 2;
    sts32(a0, fin[0]); sts32(a0 + 128, fin[1]);
    sts32(a0 + 2048, fin[2]); sts32(a0 + 2048 + 128, fin[3]);
    sts32p(a0 + 4096, fin[4], c4 == 0); sts32p(a0 + 4096 + 128, fin[5], c4 == 0);
    __syncwarp();
    if (elect_one()) mbar_arrive(bars + 8 * (B_OA + hp));
}
__device__ __forceinline__ void attn_finalize(const float (&O)[12], const uint32_t (&q)[6], int hp, uint32_t& pending, uint32_t obase, uint32_t bars,
                                              int lane) {
    const float l0 = __shfl_sync(0xffffffffu, O[8], (lane & ~3) | 1), l1 = __shfl_sync(0xffffffffu, O[10], (lane & ~3) | 1);
    uint32_t fin[6];
    const float r0 = rcp(l0), r1 = rcp(l1);
#pragma unroll
    for (int j = 0; j < 3; j++) {
        fin[2 * j] = pack(O[4 * j] * r0, O[4 * j + 1] * r0);
        fin[2 * j + 1] = pack(O[4 * j + 2] * r1, O[4 * j + 3] * r1);
    }
    float sa = 0.f;
#pragma unroll
    for (int j = 0; j < 12; j++) sa += fabsf(O[j]);
    const bool bad = !(l0 >= 0x1p-80f && l0 <= 0x1p100f && l1 >= 0x1p-80f && l1 <= 0x1p100f && sa <= 0x1p120f);
    if (__builtin_expect(__any_sync(0xffffffffu, bad), 0)) {
        uint32_t* st = g_qstash + ((size_t)(blockIdx.x * 8 + (threadIdx.x >> 5)) * 4 + hp) * 192 + lane;
#pragma unroll
        for (int i = 0; i < 6; i++) st[32 * i] = q[i];
        pending |= 1u << hp;
    } else {
        attn_store(fin, hp, obase, bars, lane);
    }
}

__device__ __forceinline__ void ostep_issue(float (&D)[40], uint32_t sb, int wg) {
    const uint32_t alo = da(sb + SM_PQ + wg * 1024);
    const uint32_t blo = da(sb + SM_BMAT) | ((1280u >> 4) << 16);
    mma_os_z(D, alo | ((2048u >> 4) << 16), 8, blo, 8);
#pragma unroll
    for (int k = 1; k < 4; k++) mma_os(D, (alo + k * 256) | ((2048u >> 4) << 16), 8, blo + k * 160, 8);
    mma_os(D, alo + 4 * 256, 8, blo + 4 * 160, 8);
}
__device__ __forceinline__ void ostep_finish(const float (&D)[40], uint32_t sb, uint32_t bars, int wg, int wi, int lane) {
    const int c4 = lane & 3;
    float r[2][4];
#pragma unroll
    for (int hi = 0; hi < 2; hi++) {
#pragma unroll
        for (int h = 0; h < 4; h++) {
            float den = __shfl_sync(0xffffffffu, D[36 + 2 * hi + (h & 1)], (lane & ~3) | (h >> 1));
            r[hi][h] = rcp(den + 1e-6f);
        }
    }
    uint32_t v[18];
#pragma unroll
    for (int j = 0; j < 9; j++) {
#pragma unroll
        for (int hi = 0; hi < 2; hi++) {
            float s;
            if (j == 0 || j == 1) s = r[hi][0];
            else if (j == 2) s = c4 < 1 ? r[hi][0] : r[hi][1];
            else if (j == 3) s = r[hi][1];
            else if (j == 4) s = c4 < 2 ? r[hi][1] : r[hi][2];
            else if (j == 5) s = r[hi][2];
            else if (j == 6) s = c4 < 3 ? r[hi][2] : r[hi][3];
            else s = r[hi][3];
            v[2 * j + hi] = pack(D[4 * j + 2 * hi] * s, D[4 * j + 2 * hi + 1] * s);
        }
    }
    const uint32_t la = sb + SM_OSB + (lane >> 4) * 2048 + (wg * 64 + wi * 16 + ((lane >> 3) & 1) * 8 + (lane & 7)) * 16;
    store_planes(v, la, 2048);
    stsm2(sb + SM_OSB + 8 * 2048 + (wg * 64 + wi * 16 + ((lane >> 3) & 1) * 8 + (lane & 7)) * 16, v[16], v[17]);
    __syncwarp();
    if (elect_one()) mbar_arrive(bars + 8 * B_OB);
}

__device__ __forceinline__ void attention(uint32_t (&Q)[4][6], uint32_t sb, uint32_t bars, int t, int wg, int wi, int lane, uint32_t peer) {
    const int g4 = lane >> 2, c4 = lane & 3;
    const int delta = 16 * wi + g4 - 2 * c4;
    const int row_local = wg * 64 + wi * 16 + g4;
    const uint32_t obase = sb + SM_OSA + row_local * 16;
    const uint32_t sd = sb & 0x3FFFFu;
    const bool own3 = wg == 1;
    const uint32_t kh0 = (sd + SM_HALO + wg * 1024) >> 4, vh0 = (sd + SM_HALOV + wg * 1024) >> 4;
    const uint32_t k3 = own3 ? (sd + SM_OWN) >> 4 : kh0 + 192, v3 = own3 ? (sd + SM_OWNV) >> 4 : vh0 + 192;
    const uint32_t p3 = own3 ? 128u : 256u;
    const uint32_t k4 = (sd + SM_OWN + wg * 1024) >> 4, v4 = (sd + SM_OWNV + wg * 1024) >> 4;

    uint32_t msk[9];
#pragma unroll
    for (int k = 0; k < 9; k++) {
        const int d = delta - 8 * (k - 1);
        msk[k] = d >= 1 ? 0xFFFFFFFFu : (d == 0 ? 0x0000FFFFu : 0u);
    }
    float X[32], Y[32], Z[32], O[12];
    uint32_t Pa[16], Pb[16], Pc[16];
    uint32_t pending = 0;
#pragma unroll
    for (int i = 0; i < 32; i++) { X[i] = 0.f; Y[i] = 0.f; Z[i] = 0.f; }
#pragma unroll
    for (int i = 0; i < 12; i++) O[i] = 0.f;
    const uint32_t zero = opaque_zero();

    auto qk = [&](float (&S)[32], const uint32_t (&q)[6], uint32_t kbase, uint32_t ps) {
        mma_qk_z(S, q[0], q[1], q[2], q[3], kbase | (ps << 16), 8);
        mma_qk(S, q[4], q[5], zero, zero, kbase + 2 * ps, 8);
    };
    auto pv = [&](const uint32_t (&P)[16], uint32_t vbase, uint32_t ps, bool zinit) {
        const uint32_t a = vbase | (8u << 16);
        if (zinit) mma_pv_z(O, P[0], P[1], P[2], P[3], a, ps); else mma_pv(O, P[0], P[1], P[2], P[3], a, ps);
#pragma unroll
        for (int k = 1; k < 4; k++) mma_pv(O, P[4 * k], P[4 * k + 1], P[4 * k + 2], P[4 * k + 3], a + 16 * k, ps);
    };
    auto ex = [&](const float (&S)[32], uint32_t (&P)[16]) {
#pragma unroll
        for (int nb = 0; nb < 8; nb++) {
            P[2 * nb] = pack(ex2(S[4 * nb]), ex2(S[4 * nb + 1]));
            P[2 * nb + 1] = pack(ex2(S[4 * nb + 2]), ex2(S[4 * nb + 3]));
        }
    };
    auto exm = [&](const float (&Sf)[32], const float (&Sd)[32], uint32_t (&Pf)[16], uint32_t (&Pd)[16]) {
#pragma unroll
        for (int nb = 0; nb < 8; nb++) {
            float p[4];
#pragma unroll
            for (int e = 0; e < 4; e++) {
                const int tau = 8 * nb + (e & 1) - 8 * (e >> 1);
                p[e] = ex2(tau <= delta ? Sd[4 * nb + e] : Sf[4 * nb + e]);
            }
            const uint32_t a = pack(p[0], p[1]), b = pack(p[2], p[3]);
            Pd[2 * nb] = a & msk[nb + 1];
            Pf[2 * nb] = a & ~msk[nb + 1];
            Pd[2 * nb + 1] = b & msk[nb];
            Pf[2 * nb + 1] = b & ~msk[nb];
        }
    };

    mbar_wait(bars + 8 * B_HALO0, 0);
    if (DEPHASE && wg == 1) { const long long t0 = clock64(); while (clock64() - t0 < DEPHASE) {} }
    pin(X); pin(Y); pin(Z); pin(O); pin(Q[0]);
    wg_fence();
    qk(Z, Q[0], kh0 + 64, 256);
    wg_commit();
#pragma unroll
    for (int h = 0; h < 4; h++) {
        if (h == 2) mbar_wait(bars + 8 * B_HALO2, 0);
        const uint32_t kh = kh0 + h * 512, vh = vh0 + h * 768;
        pin(X);
        if (h > 0) { pin(Pa); pin(Pb); }
        float D[40];
        wg_fence();
        qk(X, Q[h], kh + 128, 256);
        wg_commit();
        wg_wait<1>();
        pin(Z); pin(Pc);
        if (h > 0) {
            pv(Pa, vh0 + (h - 1) * 768, 256, false);
            pv(Pb, v4 + (h - 1) * 384, 128, false);
            wg_commit();
        }
        ex(Z, Pc);
        pin(Pc);
        pin(Z);
        wg_fence();
        qk(Z, Q[h], k3 + h * 2 * p3, p3);
        wg_commit();
        wg_wait<1>();
        pin(O); pin(X);
        if (h > 0) {
            attn_finalize(O, Q[h - 1], h - 1, pending, obase, bars, lane);
            if (h >= 2) {
                if (pending == 0 && elect_one()) {
                    const uint32_t eb = bars + 8 * (h == 2 ? B_EARLY : B_EARLY2);
                    mbar_arrive(eb); mbar_arrive_remote(eb, peer);
                }
                if (pending != 0) pending |= h == 2 ? 16u : 32u;
            }
        }
        if (h == OSH) {
            mbar_wait(bars + 8 * B_BMAT, 0);
#pragma unroll
            for (int i = 0; i < 40; i++) D[i] = 0.f;
            pin(D);
        }
        if (h == 0) mbar_wait(bars + 8 * B_HALO1, 0);
        pin(O);
        wg_fence();
        pv(Pc, vh + 64, 256, true);
        if (h == OSH) ostep_issue(D, sb, wg);
        wg_commit();
        ex(X, Pa);
        pin(Pa);
        if (h == OSH - 1) fence_async_smem();
        pin(X); pin(Y);
        wg_fence();
        qk(X, Q[h], kh, 256);
        qk(Y, Q[h], k4 + h * 256, 128);
        wg_commit();
        wg_wait<1>();
        pin(Z); pin(Pc);
        pv(Pa, vh + 128, 256, false);
        wg_commit();
        if (h == OSH) { pin(D); ostep_finish(D, sb, bars, wg, wi, lane); }
        ex(Z, Pc);
        pin(Pc);
        pin(Z);
        wg_fence();
        if (h < 3) {
            qk(Z, Q[h < 3 ? h + 1 : 3], kh0 + (h + 1) * 512 + 64, 256);
            wg_commit();
            wg_wait<1>();
        } else {
            wg_wait<0>();
        }
        pin(X); pin(Y); pin(Pa); pin(Pb);
        pv(Pc, v3 + h * 3 * p3, p3, false);
        wg_commit();
        exm(X, Y, Pa, Pb);
        pin(Pa); pin(Pb);
    }
    pin(O); pin(Pa); pin(Pb);
    wg_fence();
    pv(Pa, vh0 + 3 * 768, 256, false);
    pv(Pb, v4 + 3 * 384, 128, false);
    wg_commit();
    wg_wait<0>();
    pin(O);
    attn_finalize(O, Q[3], 3, pending, obase, bars, lane);
    if (__builtin_expect(pending != 0, 0)) {
#pragma unroll 1
        for (int hp = 0; hp < 4; hp++) {
            if (!((pending >> hp) & 1)) continue;
            const uint32_t* st = g_qstash + ((size_t)(blockIdx.x * 8 + (threadIdx.x >> 5)) * 4 + hp) * 192 + lane;
            uint32_t q[6], fin[6];
#pragma unroll
            for (int i = 0; i < 6; i++) q[i] = st[32 * i];
            attn_slow(fin, q, hp, row_local, t, sb, lane);
            attn_store(fin, hp, obase, bars, lane);
        }
        if (elect_one()) {
            if (pending & 16u) { mbar_arrive(bars + 8 * B_EARLY); mbar_arrive_remote(bars + 8 * B_EARLY, peer); }
            if (pending & 32u) { mbar_arrive(bars + 8 * B_EARLY2); mbar_arrive_remote(bars + 8 * B_EARLY2, peer); }
        }
    }
}

__device__ __forceinline__ void outproj(uint32_t sb, uint32_t bars, int wg, int wi, int lane, uint32_t peer, const CUtensorMap* tmOut, int col0, int row0) {
    float acc[72];
#pragma unroll
    for (int i = 0; i < 72; i++) acc[i] = 0.f;
    pin(acc);
    const bool elect = elect_one();
    const uint32_t sd = sb & 0x3FFFFu;
    const uint32_t eb0 = bars + 8 * B_OPEMPTY;
    uint32_t eb0r;
    asm("mapa.shared::cluster.u32 %0, %1, %2;" : "=r"(eb0r) : "r"(eb0), "r"(peer));
    int so = 0, sw = 0;
#pragma unroll 1
    for (int s = 0; s < 9; s++) {
        mbar_wait(bars + 8 * (B_WOFULL + sw), s >= OWS);
        mbar_wait(bars + 8 * (B_OPFULL + so), s >= OS);
        fence_async_smem();
        const uint32_t h0 = so == 0 ? op_o_half(0, 0) : so == 1 ? op_o_half(1, 0) : so == 2 ? op_o_half(2, 0) : so == 3 ? op_o_half(3, 0) : op_o_half(4, 0);
        const uint32_t h1 = so == 0 ? op_o_half(0, 1) : so == 1 ? op_o_half(1, 1) : so == 2 ? op_o_half(2, 1) : so == 3 ? op_o_half(3, 1) : op_o_half(4, 1);
        const uint32_t wb = sw == 0 ? op_w_slot(0) : sw == 1 ? op_w_slot(1) : sw == 2 ? op_w_slot(2) : sw == 3 ? op_w_slot(3) : op_w_slot(4);
        const uint32_t a0 = ((sd + h0 + wg * 1024) >> 4) | ((2048u >> 4) << 16), a1 = ((sd + h1 + wg * 1024) >> 4) | ((2048u >> 4) << 16);
        const uint32_t blo = ((sd + wb) >> 4) | ((8192u >> 4) << 16);
        wg_fence();
        mma_op(acc, a0, 8, blo, HI_SW128, s != 0);
        mma_op(acc, a0 + 256, 8, blo + 128, HI_SW128, 1);
        mma_op(acc, a1, 8, blo + 256, HI_SW128, 1);
        mma_op(acc, a1 + 256, 8, blo + 384, HI_SW128, 1);
        wg_commit();
        if (s > 0) {
            wg_wait<1>();
            if (elect && s <= 5) {
                if (s <= 4) {
                    mbar_arrive(eb0 + 8 * (s - 1));
                    asm volatile("mbarrier.arrive.shared::cluster.b64 _, [%0];" ::"r"(eb0r + 8 * (s - 1)) : "memory");
                }
                mbar_arrive(bars + 8 * (B_WOEMPTY + s - 1));
            }
        }
        if (++so == OS) so = 0;
        if (++sw == OWS) sw = 0;
    }
    wg_wait<0>();
    pin(acc);
    mbar_wait(bars + 8 * (B_WOEMPTY + 4), 0);
    if (wg == 1) mbar_wait(bars + 8 * B_OSAF, 0);
    const uint32_t stg = sb + (wg == 0 ? op_w_slot(4) : SM_OSA) + wi * 16 * 288;
    const uint32_t la = stg + (((lane >> 3) & 1) * 8 + (lane & 7)) * 288 + (lane >> 4) * 16;
#pragma unroll
    for (int j = 0; j < 18; j += 2)
        stsm4(la + j * 16, pack(acc[4 * j], acc[4 * j + 1]), pack(acc[4 * j + 2], acc[4 * j + 3]), pack(acc[4 * j + 4], acc[4 * j + 5]),
              pack(acc[4 * j + 6], acc[4 * j + 7]));
    __syncwarp();
    if (elect) {
        fence_async_smem();
        tma2d_store(tmOut, col0, row0 + wg * 64 + wi * 16, stg);
        bulk_commit();
        asm volatile("cp.async.bulk.wait_group.read 0;" ::: "memory");
    }
}

__device__ __forceinline__ void gemm_x_loads(const CUtensorMap* tmX, int it0, uint32_t sb, uint32_t bars, int t) {
    int xs = it0 % XS;
    uint32_t xph = ((it0 / XS) & 1) ^ 1;
#pragma unroll 1
    for (int s = 0; s < 9; s++) {
        mbar_wait(bars + 8 * (B_XEMPTY + xs), xph);
        if (it0 == 0 && s == 0) { if (++xs == XS) { xs = 0; xph ^= 1; } continue; }
        if (THROTTLE && it0 == 0 && s >= 2 && s < XS) mbar_wait(bars + 8 * (B_XFULL + s - 2), 0);
        if (elect_one()) {
            mbar_expect(bars + 8 * (B_XFULL + xs), 16384);
            tma2d(sb + xs * 16384, tmX, 64 * s, 128 * t, bars + 8 * (B_XFULL + xs));
        }
        if (++xs == XS) { xs = 0; xph ^= 1; }
        if (it0 != 0 && s == PUBLATE && elect_one()) mbar_arrive(bars + 8 * B_PUBGO);
    }
}
__device__ __forceinline__ void gemm_w_loads(const CUtensorMap* tmW, int it0, uint32_t sb, uint32_t bars, int wcol, uint32_t rank) {
    int ws = (2 * it0) % WS;
    uint32_t wph = (((2 * it0) / WS) & 1) ^ 1;
#pragma unroll 1
    for (int j = 0; j < 18; j++) {
        if (it0 == 0 && j < 2) { ++ws; continue; }
        if (THROTTLE && it0 == 0 && j >= 4 && j < WS) mbar_wait(bars + 8 * (B_WFULL + j - 4), 0);
        mbar_wait(bars + 8 * (B_WEMPTY + ws), wph);
        if (elect_one()) {
            mbar_expect(bars + 8 * (B_WFULL + ws), 12288);
            if ((j & 1) == (int)rank) tma3d_mc(sb + slot_addr_rt(XS + ws), tmW, wcol, 32 * j, 0, bars + 8 * (B_WFULL + ws));
        }
        if (++ws == WS) { ws = 0; wph ^= 1; }
    }
}
__device__ __forceinline__ void gemm_leftover_loads(const __nv_bfloat16* w, int it0, uint32_t sb, uint32_t bars, int lane) {
    int ws = (2 * it0) % WS;
    uint32_t wph = (((2 * it0) / WS) & 1) ^ 1;
    w += (size_t)lane * 1728;
#pragma unroll 1
    for (int j = 0; j < 18; j++) {
        if (it0 == 0 && j < 2) { ++ws; w += 32 * 1728; continue; }
        const uint32_t base = sb + slot_addr_rt(XS + ws) + 12288 + lane * 128;
        mbar_wait(bars + 8 * (B_WEMPTY + ws), wph);
#pragma unroll
        for (int u = 0; u < 3; u++) cp_async16(base + ((u ^ (lane & 7)) << 4), w + u * 576);
        asm volatile("cp.async.mbarrier.arrive.noinc.shared::cta.b64 [%0];" ::"r"(bars + 8 * (B_WFULL + ws)) : "memory");
        w += 32 * 1728;
        if (++ws == WS) { ws = 0; wph ^= 1; }
    }
}

__device__ __forceinline__ void op_o_loads(const CUtensorMap* tmO, bool isA, uint32_t sb, uint32_t bars, int t2, uint32_t rank, uint32_t e1) {
    int nready = 0;
    if (!isA) poll_ge(&g_cntOB[t2 * 32], NG * e1);
#pragma unroll 1
    for (int s = 0; s < 9; s++) {
        const int so = s % OS;
        const uint32_t fb = bars + 8 * (B_OPFULL + so);
        if (isA) {
            const int need = (s >> 1) < 3 ? (s >> 1) : 3;
#pragma unroll 1
            for (int it = 0; it < (1 << WAITLOG) && nready <= need; it++) {
                uint32_t c0, c1, c2, c3;
                asm volatile("ld.relaxed.gpu.global.v4.u32 {%0, %1, %2, %3}, [%4];" : "=r"(c0), "=r"(c1), "=r"(c2), "=r"(c3) : "l"(&g_cntOA[t2 * 32]) : "memory");
                const uint32_t tg = NG * e1;
                nready = (int)(c0 - tg) < 0 ? 0 : (int)(c1 - tg) < 0 ? 1 : (int)(c2 - tg) < 0 ? 2 : (int)(c3 - tg) < 0 ? 3 : 4;
                if (nready <= need) __nanosleep(20);
            }
        }
        if (s == 0) mbar_wait(bars + 8 * B_EARLY, 0);
        if (s == 1) mbar_wait(bars + 8 * B_EARLY2, 0);
        if (s == 3) mbar_wait(bars + 8 * B_ATTN, 0);
        if (s >= OS) mbar_wait(bars + 8 * (B_OPEMPTY + so), 0);
        if (elect_one()) {
            mbar_expect(fb, 16384);
            const uint32_t dst = rank ? (so == 0 ? op_o_half(0, 1) : so == 1 ? op_o_half(1, 1) : so == 2 ? op_o_half(2, 1) : so == 3 ? op_o_half(3, 1) : op_o_half(4, 1))
                                      : (so == 0 ? op_o_half(0, 0) : so == 1 ? op_o_half(1, 0) : so == 2 ? op_o_half(2, 0) : so == 3 ? op_o_half(3, 0) : op_o_half(4, 0));
            tma4d_mc(sb + dst, tmO, 0, 16 * t2, s, 4 * rank, fb);
        }
    }
}

__device__ __forceinline__ void build_bmat(uint32_t sb, uint32_t bars, int part, int lane) {
    mbar_wait(bars + 8 * B_KVTOT, 0);
    if (lane < 24) {
        const int d = 24 * part + lane, h = d / 18;
        const uint32_t dst = sb + SM_BMAT + (d >> 3) * 1280 + (d & 7) * 2;
#pragma unroll
        for (int q = 0; q < 5; q++) {
            const uint4 u = lds128(sb + SM_KVOUT + d * 80 + q * 16);
            const uint32_t w4[4] = {u.x, u.y, u.z, u.w};
#pragma unroll
            for (int e4 = 0; e4 < 4; e4++) {
                const int e = 4 * q + e4;
                if (e < 19) {
                    const int n = e < 18 ? 18 * h + e : 72 + h;
                    const __nv_bfloat16 b = __float2bfloat16(__uint_as_float(w4[e4]));
                    asm volatile("st.shared.u16 [%0], %1;" ::"r"(dst + n * 16), "h"(__bfloat16_as_ushort(b)) : "memory");
                }
            }
        }
    }
    fence_async_smem();
    __syncwarp();
    if (elect_one()) mbar_arrive(bars + 8 * B_BMAT);
}

__global__ void __cluster_dims__(2, 1, 1) __launch_bounds__(NTHREADS, 1) fused_kernel(const __grid_constant__ Params P) {
    extern __shared__ __align__(1024) uint8_t smem_raw[];
    const uint32_t sb = (uint32_t)__cvta_generic_to_shared(smem_raw);
    const uint32_t bars = sb + SM_BAR;
    const int t = blockIdx.x & 15, g = blockIdx.x >> 4;
    const uint32_t rank = blockIdx.x & 1;
    const bool opA = (blockIdx.x >> 1) & 1;
    const int t2 = blockIdx.x >> 3, opcol = 288 * ((blockIdx.x >> 2) & 1) + 144 * (blockIdx.x & 1);
    const int odd = g & 1;
    const int warp = __shfl_sync(0xffffffffu, threadIdx.x >> 5, 0);
    const int lane = threadIdx.x & 31;

    if (WPREF && warp == 10 && lane < 24) {
#pragma unroll
        for (int sl = 0; sl < WPREF; sl++) {
            const __nv_bfloat16* p = P.wA + (size_t)(64 * sl + 4 * t + lane / 6) * 1728 + ((lane % 6) >> 1) * 576 + 72 * g + (lane & 1) * 64;
            asm volatile("prefetch.global.L2 [%0];" ::"l"(p));
        }
    }
    if (threadIdx.x == 64) {
        asm volatile("prefetch.tensormap [%0];" ::"l"(&P.tmXA) : "memory");
        asm volatile("prefetch.tensormap [%0];" ::"l"(&P.tmWA) : "memory");
    }
    if (lane == 0) {
        if (warp == 8) {
#pragma unroll
            for (int i = 0; i < XS; i++) mbar_init(bars + 8 * (B_XFULL + i), 1);
        } else if (warp == 9) {
            mbar_init(bars + 8 * B_WFULL, 33);
            mbar_init(bars + 8 * (B_WFULL + 1), 33);
        } else {
#pragma unroll
            for (int k = 0; k < (B_COUNT + 9) / 10; k++) {
                const int i = (warp < 8 ? warp : warp - 2) + 10 * k;
                if (i < B_COUNT && i >= XS && i != B_WFULL && i != B_WFULL + 1) mbar_init(bars + 8 * i, bar_count(i));
            }
        }
        asm volatile("fence.mbarrier_init.release.cluster;" ::: "memory");
    }
    asm volatile("barrier.cluster.arrive.relaxed.aligned;" ::: "memory");
    if (warp == 8) {
        if (elect_one()) {
            mbar_expect(bars + 8 * B_XFULL, 16384);
            tma2d(sb, &P.tmXA, 0, 128 * t, bars + 8 * B_XFULL);
        }
    } else if (warp == 9 || warp == 10) {
        named_sync(4, 96);
        if (elect_one()) {
            const int j = warp - 9;
            mbar_expect(bars + 8 * (B_WFULL + j), 12288);
            tma3d(sb + slot_addr_rt(XS + j), &P.tmWA, 72 * g + 8 * odd, 32 * j, 0, bars + 8 * (B_WFULL + j));
        }
    } else if (warp == 11) {
        named_sync(4, 96);
        const __nv_bfloat16* w = P.wA + 72 * g + (odd ? 0 : 64) + (size_t)lane * 1728;
#pragma unroll
        for (int j = 0; j < 2; j++) {
#pragma unroll
            for (int u = 0; u < 3; u++) cp_async16(sb + slot_addr(XS + j) + 12288 + lane * 128 + ((u ^ (lane & 7)) << 4), w + (size_t)j * 32 * 1728 + u * 576);
            asm volatile("cp.async.mbarrier.arrive.noinc.shared::cta.b64 [%0];" ::"r"(bars + 8 * (B_WFULL + j)) : "memory");
        }
    }
    asm volatile("barrier.cluster.wait.aligned;" ::: "memory");

    if (warp == 8) {
        gemm_x_loads(&P.tmXA, 0, sb, bars, t);
    }
    if (warp == 9) gemm_w_loads(&P.tmWA, 0, sb, bars, 72 * g + 8 * odd, rank);
    if (warp == 11) gemm_leftover_loads(P.wA + 72 * g + (odd ? 0 : 64), 0, sb, bars, lane);

    if (__builtin_expect(warp >= 8, 1)) {
        asm volatile("setmaxnreg.dec.sync.aligned.u32 40;");
        const uint32_t e1 = __ldcg(&g_epoch[blockIdx.x]) + 1;
        if (__builtin_expect(warp == 8, 1)) {
            gemm_x_loads(&P.tmXB, 9, sb, bars, t);
            if (lane == 0) {
                if (t >= 1) poll_ge(&g_flagKV[((t - 1) * NG + g) * 8], e1);
                if (t >= 2) poll_ge(&g_flagKV[((t - 2) * NG + g) * 8], e1);
            }
            __syncwarp();
            mbar_wait(bars + 8 * B_RDONE, 0);
            if (elect_one()) {
                mbar_expect(bars + 8 * B_HALO0, 9 * 4096);
                tma4d(sb + SM_HALO, &P.tmHaloK, 0, 16 * t - 32, 0, g, bars + 8 * B_HALO0);
                mbar_expect(bars + 8 * B_HALO1, 6 * 4096);
                tma4d(sb + SM_HALOV, &P.tmHaloV, 0, 16 * t - 32, 9, g, bars + 8 * B_HALO1);
                mbar_expect(bars + 8 * B_HALO2, 6 * 4096);
                tma4d(sb + SM_HALOV + 6 * 4096, &P.tmHaloV, 0, 16 * t - 32, 15, g, bars + 8 * B_HALO2);
            }
            op_o_loads(opA ? &P.tmOA : &P.tmOB, opA, sb, bars, t2, rank, e1);
        } else if (warp == 9) {
            gemm_w_loads(&P.tmWB, 9, sb, bars, 72 * g + 8 * odd, rank);
            if (t == 0) for (int i = lane; i < 1440; i += 32) g_kvsum[(((e1 & 1)) * NG + g) * 1440 + i] = 0.f;
            mbar_wait(bars + 8 * B_RDONE, 0);
            for (int i = lane; i < 800; i += 32) sts128(sb + SM_BMAT + i * 16, make_uint4(0, 0, 0, 0));
            __syncwarp();
            float* acc = g_kvsum + ((((e1 - 1) & 1)) * NG + g) * 1440;
            mbar_wait(bars + 8 * B_KVOUT, 0);
            if (lane == 0) {
                fence_async_smem();
                bulk_reduce_f32(acc, sb + SM_KVOUT, 5760);
                bulk_commit();
                bulk_wait0();
                red_add_flag(&g_cntKV[g * 32], 1);
                poll_ge(&g_cntKV[g * 32], NT * e1);
                mbar_expect(bars + 8 * B_KVTOT, 5760);
                bulk_load(sb + SM_KVOUT, acc, 5760, bars + 8 * B_KVTOT);
            }
            __syncwarp();
            build_bmat(sb, bars, 0, lane);
            mbar_wait(bars + 8 * B_OB, 0);
            if (lane == 0) {
                fence_async_smem();
                tma3d_store(&P.tmOBst, 0, 16 * t, 9 * g, sb + SM_OSB);
                bulk_commit();
                bulk_wait0();
                red_add_flag(&g_cntOB[t * 32], 1);
                mbar_arrive(bars + 8 * B_WOGO);
            }
            __syncwarp();
#pragma unroll 1
            for (int s = 0; s < 9; s++) {
                const int so = s % OWS;
                const uint32_t dst = sb + (so == 0 ? op_w_slot(0) : so == 1 ? op_w_slot(1) : so == 2 ? op_w_slot(2) : so == 3 ? op_w_slot(3) : op_w_slot(4));
                if (s == 2) mbar_wait(bars + 8 * B_EARLY, 0);
                if (s == 3) mbar_wait(bars + 8 * B_ATTN, 0);
                if (WODELAY && s == 4) __nanosleep(WODELAY);
                if (s >= OWS) mbar_wait(bars + 8 * (B_WOEMPTY + so), 0);
                if (elect_one()) {
                    mbar_expect(bars + 8 * (B_WOFULL + so), 16384);
                    tma4d(dst, opA ? &P.tmWoA : &P.tmWoB, opcol, 0, 0, s, bars + 8 * (B_WOFULL + so));
                }
            }
        } else if (warp == 10) {
            if (lane == 0) {
                asm volatile("prefetch.tensormap [%0];" ::"l"(&P.tmXB) : "memory");
                asm volatile("prefetch.tensormap [%0];" ::"l"(&P.tmWB) : "memory");
            }
            mbar_wait(bars + 8 * B_KVPUB, 0);
            mbar_wait(bars + 8 * B_PUBGO, 0);
            if (lane == 0) {
                fence_async_smem();
#pragma unroll 1
                for (int p = 0; p < KVPIECES; p++) {
                    tma4d_store(&P.tmKVst, 0, 16 * t, (21 / KVPIECES) * p, g, sb + SM_OWN + (21 / KVPIECES) * p * 2048);
                    bulk_commit();
                    bulk_wait0();
                }
                st_flag(&g_flagKV[(t * NG + g) * 8], e1);
            }
            build_bmat(sb, bars, 1, lane);
#pragma unroll 1
            for (int b = 0; b < 4; b++) {
                mbar_wait(bars + 8 * (B_OA + b), 0);
                if (lane == 0) {
                    fence_async_smem();
                    tma3d_store(b < 3 ? &P.tmOAst2 : &P.tmOAst3, 0, 16 * t, 9 * g + 2 * b, sb + SM_OSA + 2 * b * 2048);
                    bulk_commit();
                    bulk_wait0();
                    red_add_flag(&g_cntOA[t * 32 + b], 1);
                }
            }
            if (lane == 0) {
                mbar_arrive(bars + 8 * B_OSAF);
                g_epoch[blockIdx.x] = e1;
            }
        } else {
            gemm_leftover_loads(P.wB + 72 * g + (odd ? 0 : 64), 9, sb, bars, lane);
            build_bmat(sb, bars, 2, lane);
            mbar_wait(bars + 8 * B_WOGO, 0);
            const __nv_bfloat16* wo = (opA ? P.woA : P.woB) + opcol + 128;
#pragma unroll 1
            for (int s = 0; s < 9; s++) {
                const int so = s % OWS;
                const uint32_t dst = sb + (so == 0 ? op_w_slot(0) : so == 1 ? op_w_slot(1) : so == 2 ? op_w_slot(2) : so == 3 ? op_w_slot(3) : op_w_slot(4));
                if (s == 2) mbar_wait(bars + 8 * B_EARLY, 0);
                if (s == 3) mbar_wait(bars + 8 * B_ATTN, 0);
                if (s == 4) mbar_wait(bars + 8 * B_OSAF, 0);
                if (s >= OWS) mbar_wait(bars + 8 * (B_WOEMPTY + so), 0);
#pragma unroll
                for (int u = 0; u < 4; u++) {
                    const int idx = lane + 32 * u, kk = idx >> 1, c = idx & 1;
                    const int krow = 72 * (kk >> 3) + 8 * s + (kk & 7);
                    cp_async16(dst + 16384u + kk * 128 + ((c ^ (kk & 7)) << 4), wo + (size_t)krow * 576 + 8 * c);
                }
                asm volatile("cp.async.mbarrier.arrive.noinc.shared::cta.b64 [%0];" ::"r"(bars + 8 * (B_WOFULL + so)) : "memory");
                if (elect_one()) tma4d(dst + 8192u, opA ? &P.tmWoA : &P.tmWoB, opcol + 64, 0, 0, s, bars + 8 * (B_WOFULL + so));
            }
        }
    } else {
        const int wg = warp >> 2, wi = warp & 3;
        const int c4 = lane & 3;
        const bool elect = elect_one();
        const uint32_t rowoff = (wg * 64 + wi * 16 + ((lane >> 3) & 1) * 8 + (lane & 7)) * 16;
        float acc[108];
#pragma unroll
        for (int i = 0; i < 108; i++) acc[i] = 0.f;
        pin(acc);
        gemm1_mainloop(acc, sb, bars, 0, wg, elect, rank ^ 1);
        asm volatile("setmaxnreg.inc.sync.aligned.u32 232;");
        uint32_t Q[4][6];
        {
            uint32_t qt[18], v[18];
#pragma unroll
            for (int j = 0; j < 9; j++) {
                const int nb = j < 8 ? j : 24;
                qt[2 * j] = pack(acc[4 * nb] * QSCALE, acc[4 * nb + 1] * QSCALE);
                qt[2 * j + 1] = pack(acc[4 * nb + 2] * QSCALE, acc[4 * nb + 3] * QSCALE);
            }
            rotate_planes(qt, odd);
#pragma unroll
            for (int h = 0; h < 4; h++) {
#pragma unroll
                for (int jj = 0; jj < 3; jj++) {
                    const int n = 8 * jj + 2 * c4;
                    const bool ok = n >= 2 * h && n < 2 * h + 18;
                    Q[h][2 * jj] = ok ? qt[2 * (2 * h + jj)] : 0u;
                    Q[h][2 * jj + 1] = ok ? qt[2 * (2 * h + jj) + 1] : 0u;
                }
            }
#pragma unroll
            for (int j = 0; j < 9; j++) {
                const int nb = j < 8 ? 8 + j : 25;
                v[2 * j] = pack(acc[4 * nb], acc[4 * nb + 1]);
                v[2 * j + 1] = pack(acc[4 * nb + 2], acc[4 * nb + 3]);
            }
            store_tiles(v, sb + SM_OWN, rowoff, lane, odd);
#pragma unroll
            for (int j = 0; j < 9; j++) {
                const int nb = j < 8 ? 16 + j : 26;
                v[2 * j] = pack(acc[4 * nb], acc[4 * nb + 1]);
                v[2 * j + 1] = pack(acc[4 * nb + 2], acc[4 * nb + 3]);
            }
            const uint32_t vrow = sb + SM_OWNV + (wg * 64 + wi * 16 + (lane >> 2)) * 16;
#pragma unroll
            for (int j = 0; j < 9; j++) {
                const int col = 8 * (j < 8 ? j + odd : (odd ? 0 : 8)) + 2 * c4, h = (col * 57) >> 10, d = col - 18 * h;
                const uint32_t a = vrow + (3 * h + (d >> 3)) * 2048 + (d & 7) * 2;
                sts32(a, v[2 * j]);
                sts32(a + 128, v[2 * j + 1]);
            }
#pragma unroll
            for (int u = 0; u < 2; u++) {
                const uint32_t a = sb + SM_OWNV + (3 * (2 * wg + u) + 2) * 2048 + (threadIdx.x & 127) * 16;
                sts32(a + 4, 0x00003F80u);
                asm volatile("st.shared.v2.u32 [%0], {%1, %1};" ::"r"(a + 8), "r"(0u) : "memory");
            }
            __syncwarp();
            if (elect) mbar_arrive(bars + 8 * B_KVPUB);
        }
        gemm1_mainloop(acc, sb, bars, 9, wg, elect, rank ^ 1);
        named_sync(1, 256);
        if (threadIdx.x == 0) mbar_arrive(bars + 8 * B_RDONE);
        {
            uint32_t v[18];
#pragma unroll
            for (int j = 0; j < 9; j++) {
                const int nb = j < 8 ? 16 + j : 26;
                v[2 * j] = pack(acc[4 * nb], acc[4 * nb + 1]);
                v[2 * j + 1] = pack(acc[4 * nb + 2], acc[4 * nb + 3]);
            }
            store_tiles(v, sb + SM_VB, rowoff, lane, odd);
            if (lane < 16) sts128(sb + SM_VB + 9 * 2048 + (wg * 64 + wi * 16 + lane) * 16, make_uint4(0x00003F80u, 0, 0, 0));
#pragma unroll
            for (int j = 0; j < 9; j++) {
                const int nb = j < 8 ? 8 + j : 25;
                v[2 * j] = pack(phi(acc[4 * nb]), phi(acc[4 * nb + 1]));
                v[2 * j + 1] = pack(phi(acc[4 * nb + 2]), phi(acc[4 * nb + 3]));
            }
            store_tiles(v, sb + SM_PK, rowoff, lane, odd);
            fence_async_smem();
            named_sync(1, 256);
            float D[40];
#pragma unroll
            for (int i = 0; i < 40; i++) D[i] = 0.f;
            pin(D);
            const uint32_t alo = da(sb + SM_PK + (1 - wg) * 8 * 2048) | (8u << 16);
            const uint32_t blo = da(sb + SM_VB) | (8u << 16);
            wg_fence();
            mma_kv_z(D, alo, 128, blo, 128);
#pragma unroll
            for (int k = 1; k < 8; k++) mma_kv(D, alo + 16 * k, 128, blo + 16 * k, 128);
            wg_commit();
#pragma unroll
            for (int j = 0; j < 9; j++) {
                const int nb = j < 8 ? j : 24;
                v[2 * j] = pack(phi(acc[4 * nb]), phi(acc[4 * nb + 1]));
                v[2 * j + 1] = pack(phi(acc[4 * nb + 2]), phi(acc[4 * nb + 3]));
            }
            store_tiles(v, sb + SM_PQ, rowoff, lane, odd);
            wg_wait<0>();
            pin(D);
#pragma unroll
            for (int hi = 0; hi < 2; hi++) {
                const int d = (1 - wg) * 64 + wi * 16 + (lane >> 2) + 8 * hi;
                const int h = d / 18;
#pragma unroll
                for (int nb = 0; nb < 10; nb++) {
                    const int e = nb < 9 ? 8 * nb + 2 * c4 - 18 * h : 18;
                    const bool ok = d < 72 && (nb < 9 ? (e >= 0 && e < 18) : c4 == 0);
                    sts64p(sb + SM_KVOUT + (d * 20 + e) * 4, D[4 * nb + 2 * hi], D[4 * nb + 2 * hi + 1], ok);
                }
            }
            __syncwarp();
            if (elect) mbar_arrive(bars + 8 * B_KVOUT);
        }
        attention(Q, sb, bars, t, wg, wi, lane, rank ^ 1);
        if (elect) { mbar_arrive(bars + 8 * B_ATTN); mbar_arrive_remote(bars + 8 * B_ATTN, rank ^ 1); }
        outproj(sb, bars, wg, wi, lane, rank ^ 1, &P.tmOut, (opA ? 0 : 576) + opcol, 128 * t2);
    }
}

typedef CUresult (*EncodeFn)(CUtensorMap*, CUtensorMapDataType, cuuint32_t, void*, const cuuint64_t*, const cuuint64_t*, const cuuint32_t*,
                             const cuuint32_t*, CUtensorMapInterleave, CUtensorMapSwizzle, CUtensorMapL2promotion, CUtensorMapFloatOOBfill);

void encode(EncodeFn fn, CUtensorMap* m, int rank, const void* ptr, const cuuint64_t* dims, const cuuint64_t* strides, const cuuint32_t* box,
            CUtensorMapSwizzle sw) {
    const cuuint32_t es[5] = {1, 1, 1, 1, 1};
    fn(m, CU_TENSOR_MAP_DATA_TYPE_BFLOAT16, rank, const_cast<void*>(ptr), dims, strides, box, es, CU_TENSOR_MAP_INTERLEAVE_NONE, sw,
       CU_TENSOR_MAP_L2_PROMOTION_L2_128B, CU_TENSOR_MAP_FLOAT_OOB_FILL_NONE);
}

}

extern "C" void kernel_launch(void* const* d_in, const int* in_sizes, int n_in, void* d_out, int out_size) {
    (void)in_sizes; (void)n_in; (void)out_size;
    void* fnp = nullptr;
    cudaDriverEntryPointQueryResult qr;
    cudaGetDriverEntryPoint("cuTensorMapEncodeTiled", &fnp, cudaEnableDefault, &qr);
    EncodeFn fn = (EncodeFn)fnp;
    void *oa = nullptr, *ob = nullptr;
    cudaGetSymbolAddress(&oa, g_oa);
    cudaGetSymbolAddress(&ob, g_ob);

    Params P;
    {
        const cuuint64_t d[2] = {576, 2048}, s[1] = {1152};
        const cuuint32_t b[2] = {64, 128};
        encode(fn, &P.tmXA, 2, d_in[0], d, s, b, CU_TENSOR_MAP_SWIZZLE_128B);
        encode(fn, &P.tmXB, 2, d_in[3], d, s, b, CU_TENSOR_MAP_SWIZZLE_128B);
    }
    {
        const cuuint64_t d[3] = {576, 576, 3}, s[2] = {3456, 1152};
        const cuuint32_t b[3] = {64, 32, 3};
        encode(fn, &P.tmWA, 3, d_in[1], d, s, b, CU_TENSOR_MAP_SWIZZLE_128B);
        encode(fn, &P.tmWB, 3, d_in[4], d, s, b, CU_TENSOR_MAP_SWIZZLE_128B);
    }
    {
        const cuuint64_t d[4] = {64, 256, 9, 8}, s[3] = {128, 32768, 9 * 32768};
        const cuuint32_t b[4] = {64, 16, 1, 4};
        encode(fn, &P.tmOA, 4, oa, d, s, b, CU_TENSOR_MAP_SWIZZLE_NONE);
        encode(fn, &P.tmOB, 4, ob, d, s, b, CU_TENSOR_MAP_SWIZZLE_NONE);
    }
    {
        const cuuint64_t d[4] = {576, 8, 8, 9}, s[3] = {1152, 72 * 1152, 8 * 1152};
        const cuuint32_t b[4] = {64, 8, 8, 1};
        encode(fn, &P.tmWoA, 4, d_in[2], d, s, b, CU_TENSOR_MAP_SWIZZLE_128B);
        encode(fn, &P.tmWoB, 4, d_in[5], d, s, b, CU_TENSOR_MAP_SWIZZLE_128B);
    }
    {
        const cuuint64_t d[2] = {1152, 2048}, s[1] = {2304};
        const cuuint32_t b[2] = {144, 16};
        encode(fn, &P.tmOut, 2, d_out, d, s, b, CU_TENSOR_MAP_SWIZZLE_NONE);
    }
    {
        void* kv = nullptr;
        cudaGetSymbolAddress(&kv, g_kv);
        const cuuint64_t d[4] = {64, 256, 21, 8}, s[3] = {128, 32768, 21 * 32768};
        const cuuint32_t bk[4] = {64, 32, 9, 1}, bv[4] = {64, 32, 6, 1}, bs[4] = {64, 16, 21 / KVPIECES, 1};
        encode(fn, &P.tmHaloK, 4, kv, d, s, bk, CU_TENSOR_MAP_SWIZZLE_NONE);
        encode(fn, &P.tmHaloV, 4, kv, d, s, bv, CU_TENSOR_MAP_SWIZZLE_NONE);
        encode(fn, &P.tmKVst, 4, kv, d, s, bs, CU_TENSOR_MAP_SWIZZLE_NONE);
        const cuuint64_t d3[3] = {64, 256, 72}, s3[2] = {128, 32768};
        const cuuint32_t b3[3] = {64, 16, 9}, b3a[3] = {64, 16, 2}, b3b[3] = {64, 16, 3};
        encode(fn, &P.tmOAst2, 3, oa, d3, s3, b3a, CU_TENSOR_MAP_SWIZZLE_NONE);
        encode(fn, &P.tmOAst3, 3, oa, d3, s3, b3b, CU_TENSOR_MAP_SWIZZLE_NONE);
        encode(fn, &P.tmOBst, 3, ob, d3, s3, b3, CU_TENSOR_MAP_SWIZZLE_NONE);
    }
    P.wA = (const __nv_bfloat16*)d_in[1];
    P.wB = (const __nv_bfloat16*)d_in[4];
    P.woA = (const __nv_bfloat16*)d_in[2];
    P.woB = (const __nv_bfloat16*)d_in[5];

    cudaFuncSetAttribute(fused_kernel, cudaFuncAttributeMaxDynamicSharedMemorySize, SM_TOTAL);
    fused_kernel<<<NT * NG, NTHREADS, SM_TOTAL>>>(P);
}
```
